```python
import torch

def _softmax(x, axis=-1):
    return torch.softmax(x, dim=axis)

def _gelu(x):
    return torch.nn.functional.gelu(x, approximate='tanh')

def _silu(x):
    return torch.nn.functional.silu(x)

def _sigmoid(x):
    return torch.sigmoid(x)

def _layernorm(x, axis=-1, eps=1e-05):
    m = x.mean(dim=axis, keepdim=True)
    v = x.var(dim=axis, keepdim=True, unbiased=False)
    return (x - m) / torch.sqrt(v + eps)

def _scatter_add(tgt, idx, src, axis=0):
    return tgt.clone().index_add_(axis, idx, src)

def _segment_sum(src, seg, n):
    out = torch.zeros((n,) + src.shape[1:], dtype=src.dtype)
    return out.index_add_(0, seg, src)

def _pad(x, pw):
    flat = tuple((v for pair in reversed(pw) for v in pair))
    return torch.nn.functional.pad(x, flat)
kernel_name = 'adaLN_cond__mha_block__glu_gated_bilinear__prompt'

def setup_inputs():

    _w = lambda a: (lambda t: t.to(torch.bfloat16) if t.is_floating_point() else t)(torch.as_tensor(a))

    def _A_setup():
        B, S, D, H = (1, 2048, 1024, 32)
        return {'x': _w((lambda *s: torch.randn(*s, dtype=torch.bfloat16) * 0.05)(B, S, D)), 'wqkv': _w((lambda *s: torch.randn(*s, dtype=torch.bfloat16) * 0.05)(D, 3 * D)), 'wo': _w((lambda *s: torch.randn(*s, dtype=torch.bfloat16) * 0.05)(D, D))}
    _A_in = _A_setup()

    def _B_setup():
        B, S, D, F = (1, 2048, 1024, 3584)
        return {'x': _w((lambda *s: torch.randn(*s, dtype=torch.bfloat16) * 0.05)(B, S, D)), 'w_gate': _w((lambda *s: torch.randn(*s, dtype=torch.bfloat16) * 1.6)(D, F) * D ** (-0.5)), 'w_up': _w((lambda *s: torch.randn(*s, dtype=torch.bfloat16) * 1.6)(D, F) * D ** (-0.5)), 'w_down': _w((lambda *s: torch.randn(*s, dtype=torch.bfloat16) * 1.6)(F, D) * F ** (-0.5))}
    _B_in = _B_setup()
    return {'A_x': _A_in['x'], 'A_wqkv': _A_in['wqkv'], 'A_wo': _A_in['wo'], 'B_x': _B_in['x'], 'B_w_gate': _B_in['w_gate'], 'B_w_up': _B_in['w_up'], 'B_w_down': _B_in['w_down'], 'c': _w((lambda *s: torch.randn(*s, dtype=torch.bfloat16) * 0.2)(1, 1024) * 8.0), 'w_mod': _w((lambda *s: torch.randn(*s, dtype=torch.bfloat16) * 0.2)(1024, 6 * 1024) * 1024 ** (-0.5) * 8.0)}

def reference(A_x, A_wqkv, A_wo, B_x, B_w_gate, B_w_up, B_w_down, c, w_mod):

    def _A_ref(x, wqkv, wo):
        B, S, D = x.shape
        H = 32
        Dh = D // H
        qkv = (lambda x, *d: x.permute(*d))((x @ wqkv).reshape(B, S, 3, H, Dh), 2, 0, 3, 1, 4)
        q, k, v = (qkv[0], qkv[1], qkv[2])
        scores = torch.einsum('bhqd,bhkd->bhqk', q, k) * Dh ** (-0.5)
        p = _softmax(scores, axis=-1)
        o = torch.einsum('bhqk,bhkd->bhqd', p, v)
        return (lambda x, *d: x.permute(*d))(o, 0, 2, 1, 3).reshape(B, S, D) @ wo

    def _B_ref(x, w_gate, w_up, w_down):
        g = torch.einsum('bsd,df->bsf', x, w_gate)
        u = torch.einsum('bsd,df->bsf', x, w_up)
        h = g * u
        return torch.einsum('bsf,fd->bsd', h, w_down)
    x = A_x
    mod = (_silu(c) @ w_mod).reshape(c.shape[0], 6, 1, -1)
    sa, ca, ga, sb, cb, gb = (mod[:, 0].clone(), mod[:, 1].clone(), mod[:, 2].clone(), mod[:, 3].clone(), mod[:, 4].clone(), mod[:, 5].clone())
    h = _layernorm(x, axis=-1) * (1 + ca) + sa
    x = x + ga * _A_ref(h, A_wqkv, A_wo)
    h = _layernorm(x, axis=-1) * (1 + cb) + sb
    x = x + gb * _B_ref(h, B_w_gate, B_w_up, B_w_down)
    return x
```

```cpp
#include <cuda_runtime.h>
#include <cuda_bf16.h>
#include <cuda.h>
#include <stdint.h>

typedef __nv_bfloat16 bf16;

constexpr int S_ = 2048, D_ = 1024, F_ = 3584;
constexpr float SCALE_LOG2 = 0.17677669529663687f * 1.4426950408889634f;

__device__ __align__(1024) bf16 g_h[S_ * D_];
__device__ __align__(1024) bf16 g_h2[S_ * D_];
__device__ __align__(1024) bf16 g_qkv[S_ * 3 * D_];
__device__ __align__(1024) bf16 g_ao[S_ * D_];
__device__ __align__(1024) bf16 g_hh[S_ * F_];

__device__ __forceinline__ uint32_t smem_u32(const void* p) { return (uint32_t)__cvta_generic_to_shared(p); }
__device__ __forceinline__ void mbar_init(uint32_t bar, uint32_t count) {
    asm volatile("mbarrier.init.shared::cta.b64 [%0], %1;" ::"r"(bar), "r"(count) : "memory");
}
__device__ __forceinline__ void mbar_expect_tx(uint32_t bar, uint32_t bytes) {
    asm volatile("mbarrier.arrive.expect_tx.shared::cta.b64 _, [%0], %1;" ::"r"(bar), "r"(bytes) : "memory");
}
__device__ __forceinline__ void mbar_arrive(uint32_t bar) {
    asm volatile("mbarrier.arrive.shared::cta.b64 _, [%0];" ::"r"(bar) : "memory");
}
__device__ __forceinline__ void mbar_arrive_cluster(uint32_t bar, uint32_t cta) {
    asm volatile("{\n.reg .b32 ra;\nmapa.shared::cluster.u32 ra, %0, %1;\n"
                 "mbarrier.arrive.shared::cluster.b64 _, [ra];\n}\n" ::"r"(bar), "r"(cta) : "memory");
}
__device__ __forceinline__ void mbar_wait(uint32_t bar, uint32_t parity) {
    asm volatile("{\n.reg .pred p;\n.reg .u32 n;\nmov.u32 n, 0;\nWAIT_LOOP:\n"
                 "mbarrier.try_wait.parity.shared::cta.b64 p, [%0], %1;\n"
                 "vote.sync.all.pred p, p, 0xffffffff;\n"
                 "@p bra.uni WAIT_DONE;\n"
                 "add.u32 n, n, 1;\nsetp.lt.u32 p, n, 4194304;\n@p bra.uni WAIT_LOOP;\ntrap;\nWAIT_DONE:\n}\n" ::"r"(bar), "r"(parity) : "memory");
}
__device__ __forceinline__ bool elect_one() {
    uint32_t r;
    asm volatile("{\n.reg .pred p;\nelect.sync _|p, 0xffffffff;\nselp.u32 %0, 1, 0, p;\n}\n" : "=r"(r));
    return r;
}
__device__ __forceinline__ void fence_barrier_init() { asm volatile("fence.mbarrier_init.release.cluster;" ::: "memory"); }
__device__ __forceinline__ void fence_proxy_async() { asm volatile("fence.proxy.async.shared::cta;" ::: "memory"); }
__device__ __forceinline__ void cluster_arrive() { asm volatile("barrier.cluster.arrive.relaxed.aligned;" ::: "memory"); }
__device__ __forceinline__ void cluster_wait() { asm volatile("barrier.cluster.wait.acquire.aligned;" ::: "memory"); }
__device__ __forceinline__ uint32_t cluster_ctarank() { uint32_t r; asm volatile("mov.u32 %0, %%cluster_ctarank;" : "=r"(r)); return r; }
__device__ __forceinline__ void tma_load_2d(uint32_t dst, const CUtensorMap* tm, int c0, int c1, uint32_t bar) {
    asm volatile("cp.async.bulk.tensor.2d.shared::cluster.global.mbarrier::complete_tx::bytes [%0], [%1, {%3, %4}], [%2];"
                 ::"r"(dst), "l"(tm), "r"(bar), "r"(c0), "r"(c1) : "memory");
}
__device__ __forceinline__ void tma_store_2d(const CUtensorMap* tm, uint32_t src, int c0, int c1) {
    asm volatile("cp.async.bulk.tensor.2d.global.shared::cta.bulk_group [%0, {%2, %3}], [%1];"
                 ::"l"(tm), "r"(src), "r"(c0), "r"(c1) : "memory");
}
__device__ __forceinline__ void prefetch_l2(const void* p, uint32_t bytes) {
    asm volatile("cp.async.bulk.prefetch.L2.global [%0], %1;" ::"l"(p), "r"(bytes) : "memory");
}
__device__ __forceinline__ void bulk_commit() { asm volatile("cp.async.bulk.commit_group;" ::: "memory"); }
template <int N> __device__ __forceinline__ void bulk_wait_read() { asm volatile("cp.async.bulk.wait_group.read %0;" ::"n"(N) : "memory"); }
template <int N> __device__ __forceinline__ void bulk_wait() { asm volatile("cp.async.bulk.wait_group %0;" ::"n"(N) : "memory"); }
__device__ __forceinline__ void prefetch_tmap(const CUtensorMap* tm) { asm volatile("prefetch.tensormap [%0];" ::"l"(tm) : "memory"); }
__device__ __forceinline__ void wgmma_fence() { asm volatile("wgmma.fence.sync.aligned;" ::: "memory"); }
__device__ __forceinline__ void wgmma_commit() { asm volatile("wgmma.commit_group.sync.aligned;" ::: "memory"); }
template <int N> __device__ __forceinline__ void wgmma_wait() { asm volatile("wgmma.wait_group.sync.aligned %0;" ::"n"(N) : "memory"); }
template <int R> __device__ __forceinline__ void reg_alloc() { asm volatile("setmaxnreg.inc.sync.aligned.u32 %0;" ::"n"(R)); }
template <int R> __device__ __forceinline__ void reg_dealloc() { asm volatile("setmaxnreg.dec.sync.aligned.u32 %0;" ::"n"(R)); }
__device__ __forceinline__ void named_bar_sync(int id, int n) { asm volatile("bar.sync %0, %1;" ::"r"(id), "r"(n) : "memory"); }
__device__ __forceinline__ void named_bar_arrive(int id, int n) { asm volatile("bar.arrive %0, %1;" ::"r"(id), "r"(n) : "memory"); }
__device__ __forceinline__ void pdl_wait() { asm volatile("griddepcontrol.wait;" ::: "memory"); }
__device__ __forceinline__ void pdl_launch() { asm volatile("griddepcontrol.launch_dependents;" ::: "memory"); }
__device__ __forceinline__ void stmatrix_x4(uint32_t addr, uint32_t r0, uint32_t r1, uint32_t r2, uint32_t r3) {
    asm volatile("stmatrix.sync.aligned.m8n8.x4.shared.b16 [%0], {%1, %2, %3, %4};" ::"r"(addr), "r"(r0), "r"(r1), "r"(r2), "r"(r3) : "memory");
}
__device__ __forceinline__ void ldmatrix_x4(uint32_t addr, uint32_t& r0, uint32_t& r1, uint32_t& r2, uint32_t& r3) {
    asm volatile("ldmatrix.sync.aligned.m8n8.x4.shared.b16 {%0, %1, %2, %3}, [%4];" : "=r"(r0), "=r"(r1), "=r"(r2), "=r"(r3) : "r"(addr) : "memory");
}
__device__ __forceinline__ uint32_t pack_bf16(float lo, float hi) {
    uint32_t r; asm("cvt.rn.bf16x2.f32 %0, %1, %2;" : "=r"(r) : "f"(hi), "f"(lo)); return r;
}
__device__ __forceinline__ uint32_t pack_f16(float lo, float hi) {
    uint32_t r; asm("cvt.rn.f16x2.f32 %0, %1, %2;" : "=r"(r) : "f"(hi), "f"(lo)); return r;
}
__device__ __forceinline__ uint32_t mul_bf16x2(uint32_t a, uint32_t b) {
    uint32_t r; asm("mul.rn.bf16x2 %0, %1, %2;" : "=r"(r) : "r"(a), "r"(b)); return r;
}
__device__ __forceinline__ uint32_t add_bf16x2(uint32_t a, uint32_t b) {
    uint32_t r; asm("add.rn.bf16x2 %0, %1, %2;" : "=r"(r) : "r"(a), "r"(b)); return r;
}
__device__ __forceinline__ uint32_t sub_bf16x2(uint32_t a, uint32_t b) {
    uint32_t r; asm("sub.rn.bf16x2 %0, %1, %2;" : "=r"(r) : "r"(a), "r"(b)); return r;
}
__device__ __forceinline__ uint32_t fma_bf16x2(uint32_t a, uint32_t b, uint32_t c) {
    uint32_t r; asm("fma.rn.bf16x2 %0, %1, %2, %3;" : "=r"(r) : "r"(a), "r"(b), "r"(c)); return r;
}
__device__ __forceinline__ uint32_t mapa(uint32_t addr, uint32_t cta) {
    uint32_t r; asm("mapa.shared::cluster.u32 %0, %1, %2;" : "=r"(r) : "r"(addr), "r"(cta)); return r;
}
__device__ __forceinline__ float bf_lo(uint32_t v) { return __uint_as_float(v << 16); }
__device__ __forceinline__ float bf_hi(uint32_t v) { return __uint_as_float(v & 0xffff0000u); }
__device__ __forceinline__ float bf_round(float x) { return __bfloat162float(__float2bfloat16_rn(x)); }
template <int N> __device__ __forceinline__ void fence_regs(float (&d)[N]) {
#pragma unroll
    for (int i = 0; i < N; i++) asm volatile("" : "+f"(d[i])::"memory");
}
template <int N> __device__ __forceinline__ void fence_regs(uint32_t (&d)[N]) {
#pragma unroll
    for (int i = 0; i < N; i++) asm volatile("" : "+r"(d[i])::"memory");
}
__device__ __forceinline__ uint64_t desc128(uint32_t lo) { return ((uint64_t)0x40000040u << 32) | lo; }
__device__ __forceinline__ uint64_t desc64(uint32_t lo) { return ((uint64_t)0x80000020u << 32) | lo; }


template <int TB>
__device__ __forceinline__ void wgmma_ss_n128(float (&d)[64], uint64_t da, uint64_t db, int scale_d) {
    asm volatile("{\n.reg .pred p;\nsetp.ne.b32 p, %66, 0;\n"
        "wgmma.mma_async.sync.aligned.m64n128k16.f32.bf16.bf16 {%0, %1, %2, %3, %4, %5, %6, %7, %8, %9, %10, %11, %12, %13, %14, %15, %16, %17, %18, %19, %20, %21, %22, %23, %24, %25, %26, %27, %28, %29, %30, %31, %32, %33, %34, %35, %36, %37, %38, %39, %40, %41, %42, %43, %44, %45, %46, %47, %48, %49, %50, %51, %52, %53, %54, %55, %56, %57, %58, %59, %60, %61, %62, %63}, %64, %65, p, 1, 1, 0, %67;\n}\n"
        : "+f"(d[0]), "+f"(d[1]), "+f"(d[2]), "+f"(d[3]), "+f"(d[4]), "+f"(d[5]), "+f"(d[6]), "+f"(d[7]), "+f"(d[8]), "+f"(d[9]), "+f"(d[10]),
          "+f"(d[11]), "+f"(d[12]), "+f"(d[13]), "+f"(d[14]), "+f"(d[15]), "+f"(d[16]), "+f"(d[17]), "+f"(d[18]), "+f"(d[19]), "+f"(d[20]),
          "+f"(d[21]), "+f"(d[22]), "+f"(d[23]), "+f"(d[24]), "+f"(d[25]), "+f"(d[26]), "+f"(d[27]), "+f"(d[28]), "+f"(d[29]), "+f"(d[30]),
          "+f"(d[31]), "+f"(d[32]), "+f"(d[33]), "+f"(d[34]), "+f"(d[35]), "+f"(d[36]), "+f"(d[37]), "+f"(d[38]), "+f"(d[39]), "+f"(d[40]),
          "+f"(d[41]), "+f"(d[42]), "+f"(d[43]), "+f"(d[44]), "+f"(d[45]), "+f"(d[46]), "+f"(d[47]), "+f"(d[48]), "+f"(d[49]), "+f"(d[50]),
          "+f"(d[51]), "+f"(d[52]), "+f"(d[53]), "+f"(d[54]), "+f"(d[55]), "+f"(d[56]), "+f"(d[57]), "+f"(d[58]), "+f"(d[59]), "+f"(d[60]),
          "+f"(d[61]), "+f"(d[62]), "+f"(d[63])
        : "l"(da), "l"(db), "r"(scale_d), "n"(TB));
}

template <int TB>
__device__ __forceinline__ void wgmma_ss_n192(float (&d)[96], uint64_t da, uint64_t db, int scale_d) {
    asm volatile("{\n.reg .pred p;\nsetp.ne.b32 p, %98, 0;\n"
        "wgmma.mma_async.sync.aligned.m64n192k16.f32.bf16.bf16 {%0, %1, %2, %3, %4, %5, %6, %7, %8, %9, %10, %11, %12, %13, %14, %15, %16, %17, %18, %19, %20, %21, %22, %23, %24, %25, %26, %27, %28, %29, %30, %31, %32, %33, %34, %35, %36, %37, %38, %39, %40, %41, %42, %43, %44, %45, %46, %47, %48, %49, %50, %51, %52, %53, %54, %55, %56, %57, %58, %59, %60, %61, %62, %63, %64, %65, %66, %67, %68, %69, %70, %71, %72, %73, %74, %75, %76, %77, %78, %79, %80, %81, %82, %83, %84, %85, %86, %87, %88, %89, %90, %91, %92, %93, %94, %95}, %96, %97, p, 1, 1, 0, %99;\n}\n"
        : "+f"(d[0]), "+f"(d[1]), "+f"(d[2]), "+f"(d[3]), "+f"(d[4]), "+f"(d[5]), "+f"(d[6]), "+f"(d[7]), "+f"(d[8]), "+f"(d[9]), "+f"(d[10]),
          "+f"(d[11]), "+f"(d[12]), "+f"(d[13]), "+f"(d[14]), "+f"(d[15]), "+f"(d[16]), "+f"(d[17]), "+f"(d[18]), "+f"(d[19]), "+f"(d[20]),
          "+f"(d[21]), "+f"(d[22]), "+f"(d[23]), "+f"(d[24]), "+f"(d[25]), "+f"(d[26]), "+f"(d[27]), "+f"(d[28]), "+f"(d[29]), "+f"(d[30]),
          "+f"(d[31]), "+f"(d[32]), "+f"(d[33]), "+f"(d[34]), "+f"(d[35]), "+f"(d[36]), "+f"(d[37]), "+f"(d[38]), "+f"(d[39]), "+f"(d[40]),
          "+f"(d[41]), "+f"(d[42]), "+f"(d[43]), "+f"(d[44]), "+f"(d[45]), "+f"(d[46]), "+f"(d[47]), "+f"(d[48]), "+f"(d[49]), "+f"(d[50]),
          "+f"(d[51]), "+f"(d[52]), "+f"(d[53]), "+f"(d[54]), "+f"(d[55]), "+f"(d[56]), "+f"(d[57]), "+f"(d[58]), "+f"(d[59]), "+f"(d[60]),
          "+f"(d[61]), "+f"(d[62]), "+f"(d[63]), "+f"(d[64]), "+f"(d[65]), "+f"(d[66]), "+f"(d[67]), "+f"(d[68]), "+f"(d[69]), "+f"(d[70]),
          "+f"(d[71]), "+f"(d[72]), "+f"(d[73]), "+f"(d[74]), "+f"(d[75]), "+f"(d[76]), "+f"(d[77]), "+f"(d[78]), "+f"(d[79]), "+f"(d[80]),
          "+f"(d[81]), "+f"(d[82]), "+f"(d[83]), "+f"(d[84]), "+f"(d[85]), "+f"(d[86]), "+f"(d[87]), "+f"(d[88]), "+f"(d[89]), "+f"(d[90]),
          "+f"(d[91]), "+f"(d[92]), "+f"(d[93]), "+f"(d[94]), "+f"(d[95])
        : "l"(da), "l"(db), "r"(scale_d), "n"(TB));
}

template <int TB>
__device__ __forceinline__ void wgmma_ss_n256(float (&d)[128], uint64_t da, uint64_t db, int scale_d) {
    asm volatile("{\n.reg .pred p;\nsetp.ne.b32 p, %130, 0;\n"
        "wgmma.mma_async.sync.aligned.m64n256k16.f32.bf16.bf16 {%0, %1, %2, %3, %4, %5, %6, %7, %8, %9, %10, %11, %12, %13, %14, %15, %16, %17, %18, %19, %20, %21, %22, %23, %24, %25, %26, %27, %28, %29, %30, %31, %32, %33, %34, %35, %36, %37, %38, %39, %40, %41, %42, %43, %44, %45, %46, %47, %48, %49, %50, %51, %52, %53, %54, %55, %56, %57, %58, %59, %60, %61, %62, %63, %64, %65, %66, %67, %68, %69, %70, %71, %72, %73, %74, %75, %76, %77, %78, %79, %80, %81, %82, %83, %84, %85, %86, %87, %88, %89, %90, %91, %92, %93, %94, %95, %96, %97, %98, %99, %100, %101, %102, %103, %104, %105, %106, %107, %108, %109, %110, %111, %112, %113, %114, %115, %116, %117, %118, %119, %120, %121, %122, %123, %124, %125, %126, %127}, %128, %129, p, 1, 1, 0, %131;\n}\n"
        : "+f"(d[0]), "+f"(d[1]), "+f"(d[2]), "+f"(d[3]), "+f"(d[4]), "+f"(d[5]), "+f"(d[6]), "+f"(d[7]), "+f"(d[8]), "+f"(d[9]), "+f"(d[10]),
          "+f"(d[11]), "+f"(d[12]), "+f"(d[13]), "+f"(d[14]), "+f"(d[15]), "+f"(d[16]), "+f"(d[17]), "+f"(d[18]), "+f"(d[19]), "+f"(d[20]),
          "+f"(d[21]), "+f"(d[22]), "+f"(d[23]), "+f"(d[24]), "+f"(d[25]), "+f"(d[26]), "+f"(d[27]), "+f"(d[28]), "+f"(d[29]), "+f"(d[30]),
          "+f"(d[31]), "+f"(d[32]), "+f"(d[33]), "+f"(d[34]), "+f"(d[35]), "+f"(d[36]), "+f"(d[37]), "+f"(d[38]), "+f"(d[39]), "+f"(d[40]),
          "+f"(d[41]), "+f"(d[42]), "+f"(d[43]), "+f"(d[44]), "+f"(d[45]), "+f"(d[46]), "+f"(d[47]), "+f"(d[48]), "+f"(d[49]), "+f"(d[50]),
          "+f"(d[51]), "+f"(d[52]), "+f"(d[53]), "+f"(d[54]), "+f"(d[55]), "+f"(d[56]), "+f"(d[57]), "+f"(d[58]), "+f"(d[59]), "+f"(d[60]),
          "+f"(d[61]), "+f"(d[62]), "+f"(d[63]), "+f"(d[64]), "+f"(d[65]), "+f"(d[66]), "+f"(d[67]), "+f"(d[68]), "+f"(d[69]), "+f"(d[70]),
          "+f"(d[71]), "+f"(d[72]), "+f"(d[73]), "+f"(d[74]), "+f"(d[75]), "+f"(d[76]), "+f"(d[77]), "+f"(d[78]), "+f"(d[79]), "+f"(d[80]),
          "+f"(d[81]), "+f"(d[82]), "+f"(d[83]), "+f"(d[84]), "+f"(d[85]), "+f"(d[86]), "+f"(d[87]), "+f"(d[88]), "+f"(d[89]), "+f"(d[90]),
          "+f"(d[91]), "+f"(d[92]), "+f"(d[93]), "+f"(d[94]), "+f"(d[95]), "+f"(d[96]), "+f"(d[97]), "+f"(d[98]), "+f"(d[99]), "+f"(d[100]),
          "+f"(d[101]), "+f"(d[102]), "+f"(d[103]), "+f"(d[104]), "+f"(d[105]), "+f"(d[106]), "+f"(d[107]), "+f"(d[108]), "+f"(d[109]), "+f"(d[110]),
          "+f"(d[111]), "+f"(d[112]), "+f"(d[113]), "+f"(d[114]), "+f"(d[115]), "+f"(d[116]), "+f"(d[117]), "+f"(d[118]), "+f"(d[119]), "+f"(d[120]),
          "+f"(d[121]), "+f"(d[122]), "+f"(d[123]), "+f"(d[124]), "+f"(d[125]), "+f"(d[126]), "+f"(d[127])
        : "l"(da), "l"(db), "r"(scale_d), "n"(TB));
}

__device__ __forceinline__ void wgmma_h_ss0_n64(uint32_t (&d)[16], uint64_t da, uint64_t db) {
    asm volatile("wgmma.mma_async.sync.aligned.m64n64k16.f16.f16.f16 {%0, %1, %2, %3, %4, %5, %6, %7, %8, %9, %10, %11, %12, %13, %14, %15}, %16, %17, 0, 1, 1, 0, 0;\n"
        : "=r"(d[0]), "=r"(d[1]), "=r"(d[2]), "=r"(d[3]), "=r"(d[4]), "=r"(d[5]), "=r"(d[6]), "=r"(d[7]), "=r"(d[8]), "=r"(d[9]), "=r"(d[10]), "=r"(d[11]), "=r"(d[12]), "=r"(d[13]), "=r"(d[14]), "=r"(d[15])
        : "l"(da), "l"(db));
}

__device__ __forceinline__ void wgmma_h_ss_n64(uint32_t (&d)[16], uint64_t da, uint64_t db, int scale_d) {
    asm volatile("{\n.reg .pred p;\nsetp.ne.b32 p, %18, 0;\n"
        "wgmma.mma_async.sync.aligned.m64n64k16.f16.f16.f16 {%0, %1, %2, %3, %4, %5, %6, %7, %8, %9, %10, %11, %12, %13, %14, %15}, %16, %17, p, 1, 1, 0, 0;\n}\n"
        : "+r"(d[0]), "+r"(d[1]), "+r"(d[2]), "+r"(d[3]), "+r"(d[4]), "+r"(d[5]), "+r"(d[6]), "+r"(d[7]), "+r"(d[8]), "+r"(d[9]), "+r"(d[10]), "+r"(d[11]), "+r"(d[12]), "+r"(d[13]), "+r"(d[14]), "+r"(d[15])
        : "l"(da), "l"(db), "r"(scale_d));
}

__device__ __forceinline__ void wgmma_h_rs_n40(float (&d)[20], uint32_t a0, uint32_t a1, uint32_t a2, uint32_t a3, uint64_t db) {
    asm volatile("wgmma.mma_async.sync.aligned.m64n40k16.f32.f16.f16 {%0, %1, %2, %3, %4, %5, %6, %7, %8, %9, %10, %11, %12, %13, %14, %15, %16, %17, %18, %19}, {%20, %21, %22, %23}, %24, 1, 1, 1, 1;\n"
        : "+f"(d[0]), "+f"(d[1]), "+f"(d[2]), "+f"(d[3]), "+f"(d[4]), "+f"(d[5]), "+f"(d[6]), "+f"(d[7]), "+f"(d[8]), "+f"(d[9]), "+f"(d[10]), "+f"(d[11]), "+f"(d[12]), "+f"(d[13]), "+f"(d[14]), "+f"(d[15]), "+f"(d[16]), "+f"(d[17]), "+f"(d[18]), "+f"(d[19])
        : "r"(a0), "r"(a1), "r"(a2), "r"(a3), "l"(db));
}

__device__ __align__(16) bf16 g_modb[6 * D_];
__device__ unsigned g_qkvcnt;
__device__ unsigned g_aocnt;
__device__ unsigned g_h2cnt;
__device__ unsigned g_hflag[16 * 8 * 4];
__device__ __align__(16) uint32_t g_modx[D_];
__device__ __align__(16) uint2 g_stat2[8][S_];

__device__ __forceinline__ float silu_f(float x) { return bf_round(x / (1.0f + __expf(-x))); }
__device__ __forceinline__ float silu_bf(bf16 c) { return silu_f(__bfloat162float(c)); }
__device__ __forceinline__ void fma8(float (&a)[8], float s, const uint4& v) {
    a[0] = fmaf(s, bf_lo(v.x), a[0]); a[1] = fmaf(s, bf_hi(v.x), a[1]); a[2] = fmaf(s, bf_lo(v.y), a[2]); a[3] = fmaf(s, bf_hi(v.y), a[3]);
    a[4] = fmaf(s, bf_lo(v.z), a[4]); a[5] = fmaf(s, bf_hi(v.z), a[5]); a[6] = fmaf(s, bf_lo(v.w), a[6]); a[7] = fmaf(s, bf_hi(v.w), a[7]);
}
struct LnRow { uint32_t m, h, l; };
__device__ __forceinline__ LnRow ln_finish(float mean, float var) {
    float sd, rs;
    asm("sqrt.approx.f32 %0, %1;" : "=f"(sd) : "f"(bf_round(bf_round(var) + 1e-5f)));
    asm("rcp.approx.f32 %0, %1;" : "=f"(rs) : "f"(bf_round(sd)));
    LnRow r; r.m = pack_bf16(mean, mean); r.h = pack_bf16(rs, rs);
    const float lo = rs - bf_lo(r.h);
    r.l = pack_bf16(lo, lo);
    return r;
}
__device__ __forceinline__ uint32_t ln_norm(uint32_t x, const LnRow& r) {
    const uint32_t d = sub_bf16x2(x, r.m);
    return fma_bf16x2(d, r.h, mul_bf16x2(d, r.l));
}
__device__ __forceinline__ uint32_t ln_mod(uint32_t y, uint32_t scale, uint32_t shift) {
    return add_bf16x2(mul_bf16x2(y, add_bf16x2(scale, 0x3F803F80u)), shift);
}
__device__ __forceinline__ void mma_bf16(float (&d)[4], uint32_t a0, uint32_t a1, uint32_t a2, uint32_t a3, uint32_t b0, uint32_t b1) {
    asm("mma.sync.aligned.m16n8k16.row.col.f32.bf16.bf16.f32 {%0, %1, %2, %3}, {%4, %5, %6, %7}, {%8, %9}, {%0, %1, %2, %3};"
        : "+f"(d[0]), "+f"(d[1]), "+f"(d[2]), "+f"(d[3]) : "r"(a0), "r"(a1), "r"(a2), "r"(a3), "r"(b0), "r"(b1));
}

__global__ void __launch_bounds__(256, 2) pre_kernel(const bf16* __restrict__ c, const bf16* __restrict__ w, const bf16* __restrict__ x, bf16* __restrict__ h) {
    __shared__ __align__(16) float sc[D_];
    __shared__ float red[8][16];
    pdl_launch();
    const int t = threadIdx.x, lane = t & 31;
    if (blockIdx.x < 128) {
        if (t < 4) g_hflag[blockIdx.x * 4 + t] = 0;
        if (t == 4 && blockIdx.x == 0) { g_h2cnt = 0; g_qkvcnt = 0; g_aocnt = 0; }
        const int cg = t & 1, r0 = t >> 1;
        const uint4* wp = reinterpret_cast<const uint4*>(w + (size_t)r0 * (6 * D_) + blockIdx.x * 16 + cg * 8);
        uint2 cv;
        asm volatile("ld.global.nc.v2.u32 {%0, %1}, [%2];" : "=r"(cv.x), "=r"(cv.y) : "l"(c + t * 4));
        uint4 v[8];
#pragma unroll
        for (int i = 0; i < 8; i++)
            asm volatile("ld.global.cs.v4.u32 {%0, %1, %2, %3}, [%4];" : "=r"(v[i].x), "=r"(v[i].y), "=r"(v[i].z), "=r"(v[i].w) : "l"(wp + (size_t)i * 128 * (6 * D_ / 8)));
        *reinterpret_cast<float4*>(sc + t * 4) = make_float4(silu_f(bf_lo(cv.x)), silu_f(bf_hi(cv.x)), silu_f(bf_lo(cv.y)), silu_f(bf_hi(cv.y)));
        __syncthreads();
        float a[8];
#pragma unroll
        for (int j = 0; j < 8; j++) a[j] = 0.f;
#pragma unroll
        for (int i = 0; i < 8; i++) fma8(a, sc[r0 + i * 128], v[i]);
#pragma unroll
        for (int j = 0; j < 8; j++) {
#pragma unroll
            for (int o = 2; o < 32; o <<= 1) a[j] += __shfl_xor_sync(0xffffffff, a[j], o);
        }
        if (lane < 2) {
#pragma unroll
            for (int j = 0; j < 8; j++) red[t >> 5][cg * 8 + j] = a[j];
        }
        __syncthreads();
        if (t < 8) {
            float s0 = 0.f, s1 = 0.f;
#pragma unroll
            for (int i = 0; i < 8; i++) { s0 += red[i][2 * t]; s1 += red[i][2 * t + 1]; }
            const uint32_t v2 = pack_bf16(s0, s1);
            asm volatile("st.relaxed.gpu.global.u32 [%0], %1;" ::"l"(&g_modx[blockIdx.x * 8 + t]), "r"(~v2) : "memory");
            reinterpret_cast<uint32_t*>(g_modb)[blockIdx.x * 8 + t] = v2;
        }
    } else {
        const int row = (blockIdx.x - 128) * 16 + (t >> 5) * 2;
        const uint4* xp = reinterpret_cast<const uint4*>(x + (size_t)row * D_);
        __nanosleep(1000);
        uint4 v[8];
#pragma unroll
        for (int i = 0; i < 8; i++) v[i] = xp[lane + i * 32];
#pragma unroll
        for (int r = 0; r < 2; r++) {
            float f[32];
#pragma unroll
            for (int i = 0; i < 4; i++) {
                const uint4 u = v[r * 4 + i];
                f[8 * i] = bf_lo(u.x); f[8 * i + 1] = bf_hi(u.x); f[8 * i + 2] = bf_lo(u.y); f[8 * i + 3] = bf_hi(u.y);
                f[8 * i + 4] = bf_lo(u.z); f[8 * i + 5] = bf_hi(u.z); f[8 * i + 6] = bf_lo(u.w); f[8 * i + 7] = bf_hi(u.w);
            }
            float s = 0.f;
#pragma unroll
            for (int i = 0; i < 32; i++) s += f[i];
#pragma unroll
            for (int o = 16; o; o >>= 1) s += __shfl_xor_sync(0xffffffff, s, o);
            const float mean = s * (1.0f / D_);
            float q = 0.f;
#pragma unroll
            for (int i = 0; i < 32; i++) { const float d = f[i] - mean; q = fmaf(d, d, q); }
#pragma unroll
            for (int o = 16; o; o >>= 1) q += __shfl_xor_sync(0xffffffff, q, o);
            const LnRow ln = ln_finish(mean, q * (1.0f / D_));
#pragma unroll
            for (int i = 0; i < 4; i++) {
                uint4& u = v[r * 4 + i];
                u.x = ln_norm(u.x, ln); u.y = ln_norm(u.y, ln); u.z = ln_norm(u.z, ln); u.w = ln_norm(u.w, ln);
            }
        }
        uint4* sm = reinterpret_cast<uint4*>(sc);
        {
            uint4 m; unsigned n = 0;
            do {
                asm volatile("ld.relaxed.gpu.global.v4.u32 {%0, %1, %2, %3}, [%4];" : "=r"(m.x), "=r"(m.y), "=r"(m.z), "=r"(m.w)
                             : "l"(reinterpret_cast<const uint4*>(g_modx) + t) : "memory");
                if (++n > (1u << 22)) __trap();
            } while (!__all_sync(0xffffffff, m.x && m.y && m.z && m.w));
            sm[t] = make_uint4(~m.x, ~m.y, ~m.z, ~m.w);
        }
        __syncthreads();
        uint4* op = reinterpret_cast<uint4*>(h + (size_t)row * D_);
#pragma unroll
        for (int i = 0; i < 4; i++) {
            const uint4 sh = sm[lane + i * 32], sc4 = sm[128 + lane + i * 32];
#pragma unroll
            for (int r = 0; r < 2; r++) {
                const uint4 u = v[r * 4 + i];
                op[r * 128 + lane + i * 32] = make_uint4(ln_mod(u.x, sc4.x, sh.x), ln_mod(u.y, sc4.y, sh.y), ln_mod(u.z, sc4.z, sh.z), ln_mod(u.w, sc4.w, sh.w));
            }
        }
    }
}

template <int N> struct MMA;
template <> struct MMA<128> { static __device__ __forceinline__ void ss(float (&d)[64], uint64_t a, uint64_t b, int s) { wgmma_ss_n128<1>(d, a, b, s); } };
template <> struct MMA<192> { static __device__ __forceinline__ void ss(float (&d)[96], uint64_t a, uint64_t b, int s) { wgmma_ss_n192<1>(d, a, b, s); } };
template <> struct MMA<256> { static __device__ __forceinline__ void ss(float (&d)[128], uint64_t a, uint64_t b, int s) { wgmma_ss_n256<1>(d, a, b, s); } };

__device__ __forceinline__ void copy_out(uint32_t tile, bf16* dst, int ld, int warp, int lane) {
#pragma unroll
    for (int i = 0; i < 4; i++) {
        const int r = warp * 16 + i * 4 + (lane >> 3);
        uint4 v;
        asm volatile("ld.shared.v4.b32 {%0, %1, %2, %3}, [%4];" : "=r"(v.x), "=r"(v.y), "=r"(v.z), "=r"(v.w)
                     : "r"(tile + r * 128 + (((lane & 7) ^ (r & 7)) << 4)) : "memory");
        *reinterpret_cast<uint4*>(dst + (size_t)r * ld + (lane & 7) * 8) = v;
    }
}
struct Pipe { int s; uint32_t ph; };
template <int V> struct IC { static constexpr int value = V; };

template <int N, int KB, int STAGES, int STAGE_BYTES, bool ORD, int PEEL, int ROT = 0, typename Hook>
__device__ __forceinline__ void mma_mainloop(float (&acc)[N / 2], Pipe& p, uint32_t sbase, uint32_t s_bar, int cw, int warp, Hook hook) {
    int prev = 0;
    auto arrive = [&](int st) { if (warp == 0 && elect_one()) mbar_arrive(s_bar + STAGES * 8 + st * 8); };
    auto iter = [&](bool first) {
        mbar_wait(s_bar + p.s * 8, p.ph);
        const uint32_t sa = (sbase & 0x3FFFF) + (ROT ? (p.s + ROT) & (STAGES - 1) : p.s) * STAGE_BYTES;
        const uint32_t da = ((sa + cw * 8192) >> 4) | (1u << 16), db = ((sa + 16384) >> 4) | (512u << 16);
        if (ORD) named_bar_sync(3 + cw, 256);
        wgmma_fence();
#pragma unroll
        for (int k = 0; k < 4; k++) MMA<N>::ss(acc, desc128(da + k * 2), desc128(db + k * 128), (first && k == 0) ? 0 : 1);
        wgmma_commit();
        if (ORD) named_bar_arrive(4 - cw, 256);
    };
    auto release = [&](bool first) {
        if (!first) {
            wgmma_wait<1>();
            arrive(prev);
        }
        prev = p.s;
        if (++p.s == STAGES) { p.s = 0; p.ph ^= 1; }
    };
#pragma unroll
    for (int kb = 0; kb < PEEL; kb++) { iter(kb == 0); release(kb == 0); hook(kb); }
#pragma unroll 1
    for (int kb = PEEL; kb < KB; kb++) { iter(false); release(false); }
    wgmma_wait<0>();
    arrive(prev);
    fence_regs(acc);
}

constexpr int QKV_SMEM = 4 * 40960 + 49152 + 1024 + 256;
__global__ void __launch_bounds__(384, 1) qkv_kernel(const __grid_constant__ CUtensorMap tmA, const __grid_constant__ CUtensorMap tmB,
                                                      const __grid_constant__ CUtensorMap tmC) {
    constexpr int STAGES = 4, STAGE_BYTES = 40960;
    extern __shared__ __align__(1024) uint8_t smem_raw[];
    const uint32_t sbase = (smem_u32(smem_raw) + 1023) & ~1023u;
    const uint32_t s_epi = sbase + STAGES * STAGE_BYTES;
    const uint32_t s_bar = s_epi + 49152;
    const int wid = __shfl_sync(0xffffffff, threadIdx.x >> 5, 0), wg = wid >> 2, warp = wid & 3, lane = threadIdx.x & 31;
    const int bid = blockIdx.x, tm = bid & 15, tn0 = bid >> 4;
    if (threadIdx.x == 0) {
        for (int s = 0; s < STAGES; s++) { mbar_init(s_bar + s * 8, 1); mbar_init(s_bar + STAGES * 8 + s * 8, 2); }
        mbar_init(s_bar + 64, 1); mbar_init(s_bar + 72, 1);
        fence_barrier_init();
        prefetch_tmap(&tmA); prefetch_tmap(&tmB); prefetch_tmap(&tmC);
    }
    __syncthreads();
    if (wg == 0) {
        reg_dealloc<40>();
        if (warp == 0) {
            int s = 0; uint32_t ph = 1;
            auto load_B = [&](int t, int kb, int st) {
#pragma unroll
                for (int c = 0; c < 3; c++) tma_load_2d(sbase + st * STAGE_BYTES + 16384 + c * 8192, &tmB, c * D_ + (tn0 + t * 8) * 64, kb * 64, s_bar + st * 8);
            };
            auto load_A = [&](int kb, int st) { tma_load_2d(sbase + st * STAGE_BYTES, &tmA, kb * 64, tm * 128, s_bar + st * 8); };
            if (elect_one()) {
#pragma unroll 1
                for (int i = 0; i < STAGES; i++) { mbar_expect_tx(s_bar + i * 8, STAGE_BYTES); if (i < 2) load_B(0, i, i); }
            }
            pdl_wait();
            if (elect_one()) {
#pragma unroll 1
                for (int i = 0; i < STAGES; i++) { load_A(i, i); if (i >= 2) load_B(0, i, i); }
            }
#pragma unroll 1
            for (int it = STAGES; it < 32; it++) {
                mbar_wait(s_bar + STAGES * 8 + s * 8, ph ^ 1);
                if (it == 28) pdl_launch();
                if (elect_one()) {
                    mbar_expect_tx(s_bar + s * 8, STAGE_BYTES);
                    load_A(it & 15, s);
                    load_B(it >> 4, it & 15, s);
                }
                if (++s == STAGES) { s = 0; ph ^= 1; }
            }
        } else if (warp < 3) {
            const int cw = warp - 1;
#pragma unroll 1
            for (int i = 0; i < 6; i++) {
                const int c = i < 3 ? i : i - 3;
                named_bar_sync(3 + cw * 3 + c, 160);
                if (elect_one()) {
                    tma_store_2d(&tmC, s_epi + cw * 24576 + c * 8192, c * D_ + (tn0 + (i < 3 ? 0 : 8)) * 64, tm * 128 + cw * 64);
                    bulk_commit();
                    if (i == 5) bulk_wait_read<0>();
                    if (i == 2) {
                        bulk_wait<0>();
                        mbar_arrive(s_bar + 64 + cw * 8);
                        asm volatile("fence.proxy.async.global;" ::: "memory");
                        asm volatile("red.release.gpu.global.add.u32 [%0], 1;" ::"l"(&g_qkvcnt) : "memory");
                    }
                }
                __syncwarp();
            }
        } else if (bid < 8) {
            pdl_wait();
            reinterpret_cast<uint4*>(g_modx)[bid * 32 + lane] = make_uint4(0, 0, 0, 0);
        }
    } else {
        reg_alloc<232>();
        const int cw = wg - 1;
        Pipe p{0, 0};
        const int row = warp * 16 + (lane & 7) + ((lane >> 3) & 1) * 8;
        const uint32_t st_off = row * 128;
        const int hi = lane >> 4, r7 = row & 7;
        const uint32_t se = s_epi + cw * 24576;
        auto epi_chunk = [&](const float* a, auto kind) {
#pragma unroll
            for (int j = 0; j < 4; j++) {
                uint32_t r[4];
#pragma unroll
                for (int q = 0; q < 4; q++) {
                    const float v0 = a[kind.value * 32 + j * 8 + 2 * q], v1 = a[kind.value * 32 + j * 8 + 2 * q + 1];
                    if (kind.value == 2) r[q] = pack_f16(v0, v1);
                    else {
                        const uint32_t b = pack_bf16(v0, v1);
                        r[q] = kind.value == 0 ? pack_f16(bf_lo(b) * SCALE_LOG2, bf_hi(b) * SCALE_LOG2) : pack_f16(bf_lo(b), bf_hi(b));
                    }
                }
                stmatrix_x4(se + kind.value * 8192 + st_off + (((j * 2 + hi) ^ r7) << 4), r[0], r[1], r[2], r[3]);
            }
            fence_proxy_async();
            named_bar_arrive(3 + cw * 3 + kind.value, 160);
        };
        float acc0[96], acc1[96];
        mma_mainloop<192, 16, STAGES, STAGE_BYTES, false, 1>(acc0, p, sbase, s_bar, cw, warp, [](int) {});
        mma_mainloop<192, 16, STAGES, STAGE_BYTES, false, 6>(acc1, p, sbase, s_bar, cw, warp, [&](int i) {
            if (i == 0) epi_chunk(acc0, IC<0>{});
            if (i == 2) epi_chunk(acc0, IC<1>{});
            if (i == 4) epi_chunk(acc0, IC<2>{});
        });
        mbar_wait(s_bar + 64 + cw * 8, 0);
        epi_chunk(acc1, IC<0>{}); epi_chunk(acc1, IC<1>{}); epi_chunk(acc1, IC<2>{});
    }
}

constexpr int TAIL_SMEM = 4 * 49152 + 32768 + 1024 + 256;

__global__ void __launch_bounds__(384, 1) tail_kernel(const __grid_constant__ CUtensorMap tmAO, const __grid_constant__ CUtensorMap tmWo,
                                                       const __grid_constant__ CUtensorMap tmX, const __grid_constant__ CUtensorMap tmH2,
                                                       const __grid_constant__ CUtensorMap tmWg, const __grid_constant__ CUtensorMap tmWu,
                                                       const __grid_constant__ CUtensorMap tmHHst, const __grid_constant__ CUtensorMap tmHH,
                                                       const __grid_constant__ CUtensorMap tmWd, const __grid_constant__ CUtensorMap tmOut,
                                                       const bf16* wd, bf16* h2) {
    constexpr int STAGES = 4, STAGE_BYTES = 49152, ST0 = 6, SB0 = 32768, ROT = 2;
    extern __shared__ __align__(1024) uint8_t smem_raw[];
    const uint32_t sbase = (smem_u32(smem_raw) + 1023) & ~1023u;
    const uint32_t s_epi = sbase + STAGES * STAGE_BYTES;
    const uint32_t s_bar = s_epi + 32768;
    const uint32_t s_bar0 = s_bar + 64;
    const uint32_t xbar = s_bar0 + 96, rdybar = xbar + 8, datbar = xbar + 16, sfree = xbar + 24;
    const int wid = __shfl_sync(0xffffffff, threadIdx.x >> 5, 0), wg = wid >> 2, warp = wid & 3, lane = threadIdx.x & 31;
    const int bid = blockIdx.x;
    const uint32_t rank = cluster_ctarank();
    if (threadIdx.x == 0) {
        for (int s = 0; s < STAGES; s++) { mbar_init(s_bar + s * 8, 1); mbar_init(s_bar + STAGES * 8 + s * 8, 2); }
        for (int s = 0; s < ST0; s++) { mbar_init(s_bar0 + s * 8, 1); mbar_init(s_bar0 + ST0 * 8 + s * 8, 2); }
        mbar_init(xbar, 1); mbar_init(rdybar, 1); mbar_init(datbar, 1); mbar_init(sfree, 1); mbar_init(sfree + 8, 1);
        mbar_expect_tx(datbar, 32768);
        fence_barrier_init();
        prefetch_tmap(&tmWo); prefetch_tmap(&tmAO); prefetch_tmap(&tmX); prefetch_tmap(&tmH2); prefetch_tmap(&tmWg);
        prefetch_tmap(&tmWu); prefetch_tmap(&tmHHst); prefetch_tmap(&tmHH); prefetch_tmap(&tmWd); prefetch_tmap(&tmOut);
    }
    __syncthreads();
    cluster_arrive();
    const int tm = (bid >> 1) & 15, tn4 = bid >> 5, tn3 = tn4 * 2 + rank;
    const int xcol = tn3 * 128;
    const int fcol = tn3 * 448;
    if (wg == 0) {
        reg_dealloc<40>();
        if (warp == 0) {
            auto load_B0 = [&](int i, int st) {
                const uint32_t sb = sbase + st * SB0 + 16384, fb = s_bar0 + st * 8;
                if (i < 16) { tma_load_2d(sb, &tmWo, xcol, i * 64, fb); tma_load_2d(sb + 8192, &tmWo, xcol + 64, i * 64, fb); }
                else { tma_load_2d(sb, &tmWg, fcol, (i - 16) * 64, fb); tma_load_2d(sb + 8192, &tmWu, fcol, (i - 16) * 64, fb); }
            };
            auto load_A0 = [&](int i, int st) { tma_load_2d(sbase + st * SB0, i < 16 ? &tmAO : &tmH2, (i & 15) * 64, tm * 128, s_bar0 + st * 8); };
            if (elect_one()) {
#pragma unroll 1
                for (int i = 0; i < ST0; i++) { mbar_expect_tx(s_bar0 + i * 8, SB0); if (i < 3) load_B0(i, i); }
            }
            {
                unsigned v, n = 0;
                do {
                    asm volatile("ld.acquire.gpu.global.u32 %0, [%1];" : "=r"(v) : "l"(&g_aocnt) : "memory");
                    if (++n > (1u << 22)) asm volatile("trap;");
                } while (v < 128);
                asm volatile("fence.proxy.async.global;" ::: "memory");
            }
            if (elect_one()) {
#pragma unroll 1
                for (int i = 0; i < ST0; i++) { load_A0(i, i); if (i >= 3) load_B0(i, i); }
            }
            int st = 0; uint32_t ph = 0;
#pragma unroll 1
            for (int i = ST0; i < 32; i++) {
                if (i == 16 + ST0) {
                    unsigned v, n = 0;
                    do {
                        asm volatile("ld.acquire.gpu.global.u32 %0, [%1];" : "=r"(v) : "l"(&g_h2cnt) : "memory");
                        if (++n > (1u << 22)) asm volatile("trap;");
                    } while (v < 256);
                    asm volatile("fence.proxy.async.global;" ::: "memory");
                    if (elect_one()) {
#pragma unroll 1
                        for (int q = 16; q < 16 + ST0; q++) load_A0(q, q % ST0);
                    }
                    reinterpret_cast<uint4*>(&g_stat2[tn3][tm * 128])[lane] = make_uint4(0, 0, 0, 0);
                    reinterpret_cast<uint4*>(&g_stat2[tn3][tm * 128])[lane + 32] = make_uint4(0, 0, 0, 0);
                }
                if (i == 8) pdl_wait();
                mbar_wait(s_bar0 + ST0 * 8 + st * 8, ph);
                if (elect_one()) {
                    mbar_expect_tx(s_bar0 + st * 8, SB0);
                    if (i < 16 || i >= 16 + ST0) load_A0(i, st);
                    load_B0(i, st);
                    if (i == 7) {
                        mbar_expect_tx(xbar, 32768);
#pragma unroll
                        for (int q = 0; q < 4; q++) tma_load_2d(s_epi + q * 8192, &tmX, xcol + (q & 1) * 64, tm * 128 + (q >> 1) * 64, xbar);
                    }
                }
                if (++st == ST0) { st = 0; ph ^= 1; }
            }
            auto slot = [&](int s) { return sbase + ((s + ROT) & 3) * STAGE_BYTES; };
#pragma unroll 1
            for (int it = 0; it < 48; it++) {
                const int kb = it & 15, s = it & 3, n0 = fcol + 64 + (it >> 4) * 128;
                if (it >= STAGES) mbar_wait(s_bar + STAGES * 8 + s * 8, ((it >> 2) - 1) & 1);
                else if (it == 0) { mbar_wait(s_bar0 + ST0 * 8 + 24, 0); mbar_wait(s_bar0 + ST0 * 8 + 32, 0); }
                else if (it == 1) mbar_wait(s_bar0 + ST0 * 8 + 40, 0);
                else if (it == 2) { mbar_wait(s_bar0 + ST0 * 8, 1); mbar_wait(s_bar0 + ST0 * 8 + 8, 1); }
                else mbar_wait(s_bar0 + ST0 * 8 + 16, 0);
                if (elect_one()) {
                    const uint32_t sa = slot(s), fb = s_bar + s * 8;
                    mbar_expect_tx(fb, STAGE_BYTES);
                    tma_load_2d(sa, &tmH2, kb * 64, tm * 128, fb);
                    tma_load_2d(sa + 16384, &tmWg, n0, kb * 64, fb); tma_load_2d(sa + 24576, &tmWg, n0 + 64, kb * 64, fb);
                    tma_load_2d(sa + 32768, &tmWu, n0, kb * 64, fb); tma_load_2d(sa + 40960, &tmWu, n0 + 64, kb * 64, fb);
                    if (it >= 6) prefetch_l2(wd + bid * 28672 + (it - 6) * 680, 1360);
                }
            }
            const unsigned* fp = &g_hflag[(tm * 8 + rank * 4 + (lane & 3)) * 4 + ((lane >> 2) & 3)];
            uint32_t ready = 0;
#pragma unroll 1
            for (int it = 48; it < 76; it++) {
                const int q = it - 48, tj = q < 4 ? q : 4 + ((q - 4) >> 1), s = it & 3;
                const int k0 = (rank * 4 + (tj & 3)) * 448 + (q < 4 ? 0 : (tj >> 2) * 128 - 64 + ((q - 4) & 1) * 64);
                mbar_wait(s_bar + STAGES * 8 + s * 8, ((it >> 2) - 1) & 1);
                if (elect_one()) {
                    mbar_expect_tx(s_bar + s * 8, STAGE_BYTES);
#pragma unroll
                    for (int c = 0; c < 4; c++) tma_load_2d(slot(s) + 16384 + c * 8192, &tmWd, tn4 * 256 + c * 64, k0, s_bar + s * 8);
                }
                unsigned n = 0;
                while (!((ready >> tj) & 1)) {
                    unsigned v;
                    asm volatile("ld.acquire.gpu.global.u32 %0, [%1];" : "=r"(v) : "l"(fp) : "memory");
                    ready = __ballot_sync(0xffffffff, v >= 2);
                    asm volatile("fence.proxy.async.global;" ::: "memory");
                    if (++n > (1u << 22)) asm volatile("trap;");
                }
                if (elect_one()) tma_load_2d(slot(s), &tmHH, k0, tm * 128, s_bar + s * 8);
            }
            cluster_wait();
            mbar_wait(s_bar + STAGES * 8, 0);
            if (elect_one()) mbar_arrive_cluster(rdybar, rank ^ 1);
        } else {
            if (warp < 3) {
                const int cw = warp - 1;
                const uint32_t se = s_epi + cw * 16384;
                named_bar_sync(6 + cw, 160);
                if (lane == 0) asm volatile("red.release.gpu.global.add.u32 [%0], 1;" ::"l"(&g_h2cnt) : "memory");
                __syncwarp();
#pragma unroll 1
                for (int t = 0; t < 4; t++) {
                    named_bar_sync(6 + cw, 160);
                    if (elect_one()) {
                        const int n0 = fcol + (t ? t * 128 - 64 : 0);
                        tma_store_2d(&tmHHst, se, n0, tm * 128 + cw * 64);
                        if (t) tma_store_2d(&tmHHst, se + 8192, n0 + 64, tm * 128 + cw * 64);
                        bulk_commit();
                        bulk_wait_read<0>();
                        mbar_arrive(sfree + cw * 8);
                        bulk_wait<0>();
                        asm volatile("fence.proxy.async.global;" ::: "memory");
                        asm volatile("red.release.gpu.global.add.u32 [%0], 1;" ::"l"(&g_hflag[(tm * 8 + tn3) * 4 + t]) : "memory");
                    }
                    __syncwarp();
                }
            }
            cluster_wait();
        }
    } else {
        reg_alloc<232>();
        const int cw = wg - 1;
        const int row = warp * 16 + (lane & 7) + ((lane >> 3) & 1) * 8;
        const uint32_t st_off = row * 128;
        const int hi = lane >> 4, r7 = row & 7;
        const uint32_t se = s_epi + cw * 16384;
        const uint32_t* gp = reinterpret_cast<const uint32_t*>(g_modb + xcol) + (lane & 3);
        auto nohook = [](int) {};
        if (cw == 1) named_bar_arrive(3, 256);
        uint32_t xo[32];
        Pipe p0{0, 0};
        {
            uint32_t gate[16], msc[16], msh[16];
            float acc[64];
            mma_mainloop<128, 16, ST0, SB0, false, 8>(acc, p0, sbase, s_bar0, cw, warp, [&](int i) {
                if (i != 7) return;
                pdl_wait();
#pragma unroll
                for (int j = 0; j < 16; j++) { gate[j] = gp[2 * (D_ / 2) + j * 4]; msh[j] = gp[3 * (D_ / 2) + j * 4]; msc[j] = gp[4 * (D_ / 2) + j * 4]; }
            });
#pragma unroll
            for (int j = 0; j < 16; j++) msc[j] = add_bf16x2(msc[j], 0x3F803F80u);
            mbar_wait(xbar, 0);
#pragma unroll
            for (int j = 0; j < 8; j++) {
                const int i0 = j * 8;
                uint32_t x0, x1, x2, x3;
                ldmatrix_x4(se + (j >> 2) * 8192 + st_off + ((((j & 3) * 2 + hi) ^ r7) << 4), x0, x1, x2, x3);
                xo[4 * j] = add_bf16x2(x0, mul_bf16x2(gate[2 * j], pack_bf16(acc[i0], acc[i0 + 1])));
                xo[4 * j + 1] = add_bf16x2(x1, mul_bf16x2(gate[2 * j], pack_bf16(acc[i0 + 2], acc[i0 + 3])));
                xo[4 * j + 2] = add_bf16x2(x2, mul_bf16x2(gate[2 * j + 1], pack_bf16(acc[i0 + 4], acc[i0 + 5])));
                xo[4 * j + 3] = add_bf16x2(x3, mul_bf16x2(gate[2 * j + 1], pack_bf16(acc[i0 + 6], acc[i0 + 7])));
            }
            const int grow = tm * 128 + cw * 64 + warp * 16 + (lane >> 2);
            float sm[4] = {0.f, 0.f, 0.f, 0.f}, qa[4] = {0.f, 0.f, 0.f, 0.f}, qb[4] = {0.f, 0.f, 0.f, 0.f};
#pragma unroll
            for (int j = 0; j < 8; j++) {
                mma_bf16(sm, xo[4 * j], xo[4 * j + 1], xo[4 * j + 2], xo[4 * j + 3], 0x3F803F80u, 0x3F803F80u);
                mma_bf16(qa, xo[4 * j], xo[4 * j + 1], xo[4 * j + 2], xo[4 * j + 3], xo[4 * j], xo[4 * j + 2]);
                mma_bf16(qb, xo[4 * j], xo[4 * j + 1], xo[4 * j + 2], xo[4 * j + 3], xo[4 * j + 1], xo[4 * j + 3]);
            }
            const int dsrc = (lane & 28) | (lane >> 3);
            const float q0 = __shfl_sync(0xffffffff, (lane & 4) ? qa[1] : qa[0], dsrc), q1 = __shfl_sync(0xffffffff, (lane & 4) ? qb[3] : qb[2], dsrc);
            if ((lane & 3) < 2) {
                const bool r = lane & 1;
                asm volatile("{\n.reg .b64 v;\nmov.b64 v, {%1, %2};\nst.relaxed.gpu.global.b64 [%0], v;\n}\n" ::"l"(&g_stat2[tn3][grow + (r ? 8 : 0)]),
                             "r"(__float_as_uint(r ? sm[2] : sm[0])), "r"(~__float_as_uint(r ? q1 : q0)) : "memory");
            }
            uint2 a, b, c, d;
            asm volatile("{\n.reg .pred p;\n.reg .u32 n, t;\n.reg .b64 a, b, c, d;\nmov.u32 n, 0;\nPOLL:\n"
                         "ld.relaxed.gpu.global.b64 a, [%8];\nld.relaxed.gpu.global.b64 b, [%8 + 16384];\n"
                         "ld.relaxed.gpu.global.b64 c, [%8 + 64];\nld.relaxed.gpu.global.b64 d, [%8 + 16448];\n"
                         "mov.b64 {%0, %1}, a;\nmov.b64 {%2, %3}, b;\nmov.b64 {%4, %5}, c;\nmov.b64 {%6, %7}, d;\n"
                         "min.u32 t, %1, %3;\nmin.u32 t, t, %5;\nmin.u32 t, t, %7;\nsetp.ne.u32 p, t, 0;\n"
                         "vote.sync.all.pred p, p, 0xffffffff;\n@p bra.uni DONE;\n"
                         "add.u32 n, n, 1;\nsetp.lt.u32 p, n, 4194304;\n@p bra.uni POLL;\ntrap;\nDONE:\n}\n"
                         : "=r"(a.x), "=r"(a.y), "=r"(b.x), "=r"(b.y), "=r"(c.x), "=r"(c.y), "=r"(d.x), "=r"(d.y)
                         : "l"(&g_stat2[(lane & 3) * 2][grow]) : "memory");
            float2 u0 = make_float2(__uint_as_float(a.x) + __uint_as_float(b.x), __uint_as_float(~a.y) + __uint_as_float(~b.y));
            float2 u1 = make_float2(__uint_as_float(c.x) + __uint_as_float(d.x), __uint_as_float(~c.y) + __uint_as_float(~d.y));
#pragma unroll
            for (int o = 1; o < 4; o <<= 1) {
                u0.x += __shfl_xor_sync(0xffffffff, u0.x, o); u0.y += __shfl_xor_sync(0xffffffff, u0.y, o);
                u1.x += __shfl_xor_sync(0xffffffff, u1.x, o); u1.y += __shfl_xor_sync(0xffffffff, u1.y, o);
            }
            const float m0 = u0.x * (1.0f / D_), m1 = u1.x * (1.0f / D_);
            const LnRow l0 = ln_finish(m0, fmaxf(u0.y * (1.0f / D_) - m0 * m0, 0.f)), l1 = ln_finish(m1, fmaxf(u1.y * (1.0f / D_) - m1 * m1, 0.f));
#pragma unroll
            for (int j = 0; j < 8; j++)
                stmatrix_x4(se + (j >> 2) * 8192 + st_off + ((((j & 3) * 2 + hi) ^ r7) << 4),
                            add_bf16x2(mul_bf16x2(ln_norm(xo[4 * j], l0), msc[2 * j]), msh[2 * j]), add_bf16x2(mul_bf16x2(ln_norm(xo[4 * j + 1], l1), msc[2 * j]), msh[2 * j]),
                            add_bf16x2(mul_bf16x2(ln_norm(xo[4 * j + 2], l0), msc[2 * j + 1]), msh[2 * j + 1]), add_bf16x2(mul_bf16x2(ln_norm(xo[4 * j + 3], l1), msc[2 * j + 1]), msh[2 * j + 1]));
            __syncwarp();
            copy_out(se, h2 + (size_t)(tm * 128 + cw * 64) * D_ + xcol, D_, warp, lane);
            copy_out(se + 8192, h2 + (size_t)(tm * 128 + cw * 64) * D_ + xcol + 64, D_, warp, lane);
            named_bar_arrive(6 + cw, 160);
        }
        {
            float acc[64];
            mma_mainloop<128, 16, ST0, SB0, false, 1>(acc, p0, sbase, s_bar0, cw, warp, nohook);
#pragma unroll
            for (int j = 0; j < 4; j++) {
                const int i0 = j * 8;
                uint32_t r[4];
#pragma unroll
                for (int q = 0; q < 4; q++) r[q] = mul_bf16x2(pack_bf16(acc[i0 + 2 * q], acc[i0 + 2 * q + 1]), pack_bf16(acc[32 + i0 + 2 * q], acc[32 + i0 + 2 * q + 1]));
                stmatrix_x4(se + st_off + (((j * 2 + hi) ^ r7) << 4), r[0], r[1], r[2], r[3]);
            }
            fence_proxy_async();
            named_bar_arrive(6 + cw, 160);
        }
        Pipe p{0, 0};
#pragma unroll 1
        for (int t = 1; t < 4; t++) {
            float acc[128];
            mma_mainloop<256, 16, STAGES, STAGE_BYTES, true, 1, ROT>(acc, p, sbase, s_bar, cw, warp, nohook);
            mbar_wait(sfree + cw * 8, (t - 1) & 1);
#pragma unroll
            for (int j = 0; j < 8; j++) {
                const int i0 = j * 8;
                uint32_t r[4];
#pragma unroll
                for (int q = 0; q < 4; q++) r[q] = mul_bf16x2(pack_bf16(acc[i0 + 2 * q], acc[i0 + 2 * q + 1]), pack_bf16(acc[64 + i0 + 2 * q], acc[64 + i0 + 2 * q + 1]));
                stmatrix_x4(se + (j >> 2) * 8192 + st_off + ((((j & 3) * 2 + hi) ^ r7) << 4), r[0], r[1], r[2], r[3]);
            }
            fence_proxy_async();
            named_bar_arrive(6 + cw, 160);
        }
        cluster_wait();
        uint32_t gate[16];
#pragma unroll
        for (int j = 0; j < 16; j++) gate[j] = gp[5 * (D_ / 2) + j * 4];
        float acc[64];
        {
            float full[128];
            mma_mainloop<256, 28, STAGES, STAGE_BYTES, true, 2, ROT>(full, p, sbase, s_bar, cw, warp, [&](int i) { if (i == 1) fence_regs(gate); });
            mbar_wait(s_bar + STAGES * 8 + 8, 0);
            const uint32_t xs = sbase + cw * 16384 + (threadIdx.x & 127) * 16;
            auto send = [&](const float* v) {
#pragma unroll
                for (int i = 0; i < 8; i++)
                    asm volatile("st.shared.v4.b32 [%0], {%1, %2, %3, %4};" ::"r"(xs + 3 * STAGE_BYTES + i * 2048), "r"(pack_bf16(v[8 * i], v[8 * i + 1])),
                                 "r"(pack_bf16(v[8 * i + 2], v[8 * i + 3])), "r"(pack_bf16(v[8 * i + 4], v[8 * i + 5])), "r"(pack_bf16(v[8 * i + 6], v[8 * i + 7])) : "memory");
            };
            if (rank == 0) {
                send(full + 64);
#pragma unroll
                for (int i = 0; i < 64; i++) acc[i] = full[i];
            } else {
                send(full);
#pragma unroll
                for (int i = 0; i < 64; i++) acc[i] = full[64 + i];
            }
            fence_proxy_async();
            named_bar_sync(1 + cw, 128);
            if (warp == 0) {
                mbar_wait(rdybar, 0);
                if (elect_one())
                    asm volatile("cp.async.bulk.shared::cluster.shared::cta.mbarrier::complete_tx::bytes [%0], [%1], %2, [%3];"
                                 ::"r"(mapa(sbase + 2 * STAGE_BYTES + cw * 16384, rank ^ 1)), "r"(sbase + 3 * STAGE_BYTES + cw * 16384), "r"(16384), "r"(mapa(datbar, rank ^ 1)) : "memory");
            }
            mbar_wait(sfree + cw * 8, 1);
            mbar_wait(datbar, 0);
#pragma unroll
            for (int i = 0; i < 8; i++) {
                uint4 v;
                asm volatile("ld.shared.v4.b32 {%0, %1, %2, %3}, [%4];" : "=r"(v.x), "=r"(v.y), "=r"(v.z), "=r"(v.w) : "r"(xs + 2 * STAGE_BYTES + i * 2048) : "memory");
                acc[8 * i] += bf_lo(v.x); acc[8 * i + 1] += bf_hi(v.x); acc[8 * i + 2] += bf_lo(v.y); acc[8 * i + 3] += bf_hi(v.y);
                acc[8 * i + 4] += bf_lo(v.z); acc[8 * i + 5] += bf_hi(v.z); acc[8 * i + 6] += bf_lo(v.w); acc[8 * i + 7] += bf_hi(v.w);
            }
        }
#pragma unroll
        for (int j = 0; j < 8; j++) {
            const int i0 = j * 8;
            stmatrix_x4(se + (j >> 2) * 8192 + st_off + ((((j & 3) * 2 + hi) ^ r7) << 4),
                        add_bf16x2(xo[4 * j], mul_bf16x2(gate[2 * j], pack_bf16(acc[i0], acc[i0 + 1]))),
                        add_bf16x2(xo[4 * j + 1], mul_bf16x2(gate[2 * j], pack_bf16(acc[i0 + 2], acc[i0 + 3]))),
                        add_bf16x2(xo[4 * j + 2], mul_bf16x2(gate[2 * j + 1], pack_bf16(acc[i0 + 4], acc[i0 + 5]))),
                        add_bf16x2(xo[4 * j + 3], mul_bf16x2(gate[2 * j + 1], pack_bf16(acc[i0 + 6], acc[i0 + 7]))));
        }
        fence_proxy_async();
        named_bar_sync(1 + cw, 128);
        if ((threadIdx.x & 127) == 0) {
#pragma unroll
            for (int c = 0; c < 2; c++) tma_store_2d(&tmOut, se + c * 8192, xcol + c * 64, tm * 128 + cw * 64);
            bulk_commit();
            bulk_wait_read<0>();
        }
    }
    cluster_arrive(); cluster_wait();
}

constexpr int ANST = 8;
constexpr int ATTN_SMEM = ANST * 16384 + 32768 + 8192 + 1024 + 256;
constexpr uint32_t PMASK = 0x13131313u;

__device__ bf16 g_fb[S_ * 3 * D_];

__device__ __forceinline__ float ex2f(float x) { float y; asm("ex2.approx.ftz.f32 %0, %1;" : "=f"(y) : "f"(x)); return y; }
__device__ __forceinline__ uint32_t h2sub(uint32_t a, uint32_t b) { uint32_t r; asm("sub.rn.f16x2 %0, %1, %2;" : "=r"(r) : "r"(a), "r"(b)); return r; }
__device__ __forceinline__ uint32_t h2fma(uint32_t a, uint32_t b, uint32_t c) { uint32_t r; asm("fma.rn.f16x2 %0, %1, %2, %3;" : "=r"(r) : "r"(a), "r"(b), "r"(c)); return r; }
__device__ __forceinline__ uint32_t h2max(uint32_t a, uint32_t b) { uint32_t r; asm("max.f16x2 %0, %1, %2;" : "=r"(r) : "r"(a), "r"(b)); return r; }
__device__ __forceinline__ uint32_t h2ex2(uint32_t a) { uint32_t r; asm("ex2.approx.f16x2 %0, %1;" : "=r"(r) : "r"(a)); return r; }
__device__ __forceinline__ float h2lo(uint32_t a) { float r; asm("{.reg .b16 l, h; mov.b32 {l, h}, %1; cvt.f32.f16 %0, l;}" : "=f"(r) : "r"(a)); return r; }
__device__ __forceinline__ uint32_t h2ex2_fma(uint32_t s, uint32_t lo, uint32_t c) {
    s = h2max(s, lo);
    const uint32_t r = h2fma(s, 0x38003800u, c);
    const uint32_t f = h2fma(s, 0x38003800u, h2sub(c, r));
    uint32_t p = h2fma(f, 0x2B102B10u, 0x33C333C3u);
    p = h2fma(p, f, 0x398C398Cu);
    p = h2fma(p, f, 0x3C003C00u);
    const uint32_t z = p + (r << 10) - (0x01900000u + 0x3C003C00u);
    uint32_t y; asm("mul.rn.f16x2 %0, %1, %1;" : "=r"(y) : "r"(z));
    return y;
}
struct RowState { uint32_t m, th, lo, c; float mf; };
__device__ __forceinline__ void row_set(RowState& r, float mf) {
    r.mf = mf; r.m = pack_f16(mf, mf); r.th = pack_f16(mf + 15.f, mf + 15.f); r.lo = pack_f16(mf - 26.f, mf - 26.f);
    r.c = pack_f16(1039.f - 0.5f * mf, 1039.f - 0.5f * mf);
}
__device__ __forceinline__ void local_max(const uint32_t (&T)[16], uint32_t& a0, uint32_t& a1) {
    a0 = T[0]; a1 = T[1];
#pragma unroll
    for (int i = 2; i < 16; i += 2) { a0 = h2max(a0, T[i]); a1 = h2max(a1, T[i + 1]); }
}
__device__ __forceinline__ void quad_max(uint32_t a0, uint32_t a1, float& f0, float& f1) {
    uint32_t a = h2max(__byte_perm(a0, a1, 0x5410), __byte_perm(a0, a1, 0x7632));
    a = h2max(a, __shfl_xor_sync(0xffffffff, a, 1));
    a = h2max(a, __shfl_xor_sync(0xffffffff, a, 2));
    f0 = 2.f * rintf(0.5f * h2lo(a)) + 6.f; f1 = 2.f * rintf(0.5f * h2lo(a >> 16)) + 6.f;
}
template <uint32_t PM, int K>
__device__ __forceinline__ void exp_pv(const uint32_t (&T)[16], float (&O)[20], const RowState& r0, const RowState& r1, uint64_t dv) {
    uint32_t p[4];
#pragma unroll
    for (int i = 0; i < 4; i++) {
        const RowState& r = (i & 1) ? r1 : r0;
        p[i] = ((PM >> (4 * K + i)) & 1) ? h2ex2_fma(T[4 * K + i], r.lo, r.c) : h2ex2(h2sub(T[4 * K + i], r.m));
    }
    wgmma_fence();
    wgmma_h_rs_n40(O, p[0], p[1], p[2], p[3], dv + K * 64);
}
template <uint32_t PM>
__device__ __forceinline__ void attn_step(uint32_t (&T)[16], uint32_t (&N)[16], float (&O)[20], RowState& r0, RowState& r1,
                                          uint64_t dv, uint64_t dq, uint64_t dq2, uint64_t dk) {
    wgmma_fence();
    wgmma_h_ss0_n64(N, dq, dk); wgmma_h_ss_n64(N, dq2, dk + 2, 1);
    wgmma_commit();
    uint32_t a0, a1;
    local_max(T, a0, a1);
    if (__any_sync(0xffffffff, (h2max(a0, r0.th) != r0.th) | (h2max(a1, r1.th) != r1.th))) {
        float f0, f1;
        quad_max(a0, a1, f0, f1);
        f0 = fmaxf(f0, r0.mf); f1 = fmaxf(f1, r1.mf);
        const float s0 = ex2f(r0.mf - f0), s1 = ex2f(r1.mf - f1);
        row_set(r0, f0); row_set(r1, f1);
#pragma unroll
        for (int q = 0; q < 5; q++) { O[4 * q] *= s0; O[4 * q + 1] *= s0; O[4 * q + 2] *= s1; O[4 * q + 3] *= s1; }
    }
    exp_pv<PM, 0>(T, O, r0, r1, dv); exp_pv<PM, 1>(T, O, r0, r1, dv); exp_pv<PM, 2>(T, O, r0, r1, dv); exp_pv<PM, 3>(T, O, r0, r1, dv);
    wgmma_commit();
}
__device__ __forceinline__ uint32_t mbar_try(uint32_t bar, uint32_t parity) {
    uint32_t ok;
    asm volatile("{\n.reg .pred p;\nmbarrier.try_wait.parity.shared::cta.b64 p, [%1], %2;\nselp.b32 %0, 1, 0, p;\n}\n" : "=r"(ok) : "r"(bar), "r"(parity) : "memory");
    return ok;
}

__device__ __forceinline__ bool bar_red_or(bool v) {
    uint32_t r;
    asm volatile("{\n.reg .pred p, q;\nsetp.ne.u32 p, %1, 0;\nbarrier.cta.red.or.pred q, 5, 512, p;\nselp.u32 %0, 1, 0, q;\n}\n" : "=r"(r) : "r"((uint32_t)v) : "memory");
    return r;
}
__device__ __noinline__ void attn_fallback(uint8_t* smem, const bf16* h, const bf16* wqkv, bf16* ao, int head, int q0) {
    const int tid = threadIdx.x, lane = tid & 31, wid = tid >> 5;
    for (int part = 0; part < 3; part++) {
        const int col = part * D_ + head * 32 + lane, r0 = part == 0 ? q0 : 0, nr = part == 0 ? 256 : S_;
        float* ws = reinterpret_cast<float*>(smem);
        named_bar_sync(5, 512);
        for (int i = tid; i < D_ * 32; i += 512) ws[i] = __bfloat162float(wqkv[(size_t)(i >> 5) * (3 * D_) + part * D_ + head * 32 + (i & 31)]);
        named_bar_sync(5, 512);
        for (int r = r0 + wid; r < r0 + nr; r += 16) {
            float acc = 0.f;
            for (int k0 = 0; k0 < D_; k0 += 32) {
                const float hv = __bfloat162float(h[(size_t)r * D_ + k0 + lane]);
#pragma unroll
                for (int k = 0; k < 32; k++) acc = fmaf(__shfl_sync(0xffffffff, hv, k), ws[(k0 + k) * 32 + lane], acc);
            }
            g_fb[(size_t)r * (3 * D_) + col] = __float2bfloat16_rn(acc);
        }
    }
    __threadfence();
    named_bar_sync(5, 512);
    const int row = q0 + (tid >> 1), par = tid & 1;
    float q[32], o[32], m = -INFINITY, l = 0.f;
#pragma unroll
    for (int d = 0; d < 32; d++) { q[d] = __bfloat162float(__ldcg(&g_fb[(size_t)row * (3 * D_) + head * 32 + d])) * SCALE_LOG2; o[d] = 0.f; }
    float* ks = reinterpret_cast<float*>(smem);
    for (int kb = 0; kb < S_; kb += 128) {
        named_bar_sync(5, 512);
        for (int i = tid; i < 128 * 64; i += 512) {
            const int r = i >> 6, c = i & 63;
            ks[i] = __bfloat162float(__ldcg(&g_fb[(size_t)(kb + r) * (3 * D_) + (1 + (c >> 5)) * D_ + head * 32 + (c & 31)]));
        }
        named_bar_sync(5, 512);
        for (int j = par; j < 128; j += 2) {
            float s = 0.f;
#pragma unroll
            for (int d = 0; d < 32; d++) s = fmaf(q[d], ks[j * 64 + d], s);
            const float mn = fmaxf(m, s), sc = exp2f(m - mn), p = exp2f(s - mn);
            l = l * sc + p; m = mn;
#pragma unroll
            for (int d = 0; d < 32; d++) o[d] = o[d] * sc + p * ks[j * 64 + 32 + d];
        }
    }
    const float m2 = __shfl_xor_sync(0xffffffff, m, 1), mn = fmaxf(m, m2), sc = exp2f(m - mn);
    l *= sc; l += __shfl_xor_sync(0xffffffff, l, 1);
#pragma unroll
    for (int d = 0; d < 32; d++) {
        float v = o[d] * sc; v += __shfl_xor_sync(0xffffffff, v, 1);
        if ((d & 1) == par) ao[(size_t)row * D_ + head * 32 + d] = __float2bfloat16_rn(v / l);
    }
    named_bar_sync(5, 512);
}

__global__ void __launch_bounds__(544, 1) attn_kernel(const __grid_constant__ CUtensorMap tmQKV, const __grid_constant__ CUtensorMap tmO,
                                                       const bf16* __restrict__ h, const bf16* __restrict__ wqkv, bf16* __restrict__ ao,
                                                       const bf16* __restrict__ c, const bf16* __restrict__ wmod,
                                                       const bf16* wo, const bf16* wgate, const bf16* wup) {
    extern __shared__ __align__(1024) uint8_t smem_raw[];
    const uint32_t sbase = (smem_u32(smem_raw) + 1023) & ~1023u;
    const uint32_t s_q = sbase + ANST * 16384;
    const uint32_t s_ones = s_q + 32768;
    const uint32_t s_bar = s_ones + 8192;
    const uint32_t qbar = s_bar + 2 * ANST * 8;
    const int tid = threadIdx.x, wid = __shfl_sync(0xffffffff, tid >> 5, 0), wg = wid >> 2, lane = tid & 31, warp = wid & 3;
    if (blockIdx.x < 4) {
        if (wid == 16) return;
        float* sc = reinterpret_cast<float*>(smem_raw);
        for (int i = tid; i < D_; i += 512) sc[i] = silu_bf(c[i]);
        named_bar_sync(1, 512);
        const int cg = tid & 127, rg = tid >> 7;
        const uint4* wp = reinterpret_cast<const uint4*>(wmod + (size_t)rg * (6 * D_) + (2 + blockIdx.x) * D_ + cg * 8);
        float a[8];
#pragma unroll
        for (int j = 0; j < 8; j++) a[j] = 0.f;
#pragma unroll 1
        for (int r = 0; r < 256; r += 16) {
            uint4 v[16];
#pragma unroll
            for (int i = 0; i < 16; i++) v[i] = __ldcs(wp + (size_t)(r + i) * 4 * (6 * D_ / 8));
#pragma unroll
            for (int i = 0; i < 16; i++) fma8(a, sc[(r + i) * 4 + rg], v[i]);
        }
#pragma unroll
        for (int j = 0; j < 8; j++) sc[D_ + rg * D_ + cg * 8 + j] = a[j];
        named_bar_sync(1, 512);
        pdl_wait();
        for (int i = tid; i < D_; i += 512) g_modb[(2 + blockIdx.x) * D_ + i] = __float2bfloat16_rn(sc[D_ + i] + sc[2 * D_ + i] + sc[3 * D_ + i] + sc[4 * D_ + i]);
        return;
    }
    const int head0 = (blockIdx.x - 4) >> 3, qbase = ((blockIdx.x - 4) & 7) * 256;
    auto head_of = [&](int pass) { return head0 + pass * 16; };
    if (tid == 0) { prefetch_tmap(&tmQKV); prefetch_tmap(&tmO); }
    auto load_kv = [&](int j) {
        const int s = j & (ANST - 1), r = (j & 15) * 128, hc = head_of((j >> 4) & 1) * 32;
        mbar_expect_tx(s_bar + s * 8, 16384);
        tma_load_2d(sbase + s * 16384, &tmQKV, 1024 + hc, r, s_bar + s * 8);
        tma_load_2d(sbase + s * 16384 + 8192, &tmQKV, 2048 + hc, r, s_bar + s * 8);
    };
    if (tid < 512) {
        asm volatile("st.shared.v4.b32 [%0], {%1, %1, %1, %1};" ::"r"(s_ones + tid * 16), "r"(0x3C003C00u) : "memory");
        fence_proxy_async();
    } else {
        unsigned v, n = 0;
        do {
            asm volatile("ld.acquire.gpu.global.u32 %0, [%1];" : "=r"(v) : "l"(&g_qkvcnt) : "memory");
            if (++n > (1u << 22)) asm volatile("trap;");
        } while (v < 256);
        asm volatile("fence.proxy.async.global;" ::: "memory");
        if (elect_one()) {
            for (int s = 0; s < ANST; s++) { mbar_init(s_bar + s * 8, 1); mbar_init(s_bar + ANST * 8 + s * 8, 16); }
            mbar_init(qbar, 1); mbar_init(qbar + 8, 1);
            asm volatile("st.shared.u32 [%0], 0;" ::"r"(qbar + 16) : "memory");
            fence_barrier_init();
            fence_proxy_async();
            mbar_expect_tx(qbar, 16384);
            for (int i = 0; i < 2; i++) tma_load_2d(s_q + i * 8192, &tmQKV, head_of(0) * 32, qbase + i * 128, qbar);
            load_kv(0);
        }
    }
    __syncthreads();
    if (wid == 16) {
        if (elect_one()) { for (int j = 1; j < ANST; j++) load_kv(j); }
        pdl_wait();
        if (elect_one()) {
            mbar_expect_tx(qbar + 8, 16384);
            for (int i = 0; i < 2; i++) tma_load_2d(s_q + 16384 + i * 8192, &tmQKV, head_of(1) * 32, qbase + i * 128, qbar + 8);
        }
#pragma unroll 1
        for (int j = ANST; j <= 32; j++) {
            mbar_wait(s_bar + ANST * 8 + (j & (ANST - 1)) * 8, ((j >> 3) - 1) & 1);
            if (elect_one()) {
                load_kv(j);
                const int b = blockIdx.x - 4, jo = j - ANST;
                if (jo < 16) {
                    prefetch_l2(wo + b * 8192 + jo * 512, 1024);
                    prefetch_l2(wgate + b * 28672 + jo * 1792, 3584);
                    prefetch_l2(wup + b * 28672 + jo * 1792, 3584);
                }
            }
            if (j == 24) {
                for (int w = 0; w < 4; w++) named_bar_sync(6 + w, 160);
                uint32_t redo;
                asm volatile("ld.shared.u32 %0, [%1];" : "=r"(redo) : "r"(qbar + 16) : "memory");
                if (elect_one()) {
                    for (int w = 0; w < 4; w++) tma_store_2d(&tmO, s_q + w * 4096, head0 * 32, qbase + w * 64);
                    bulk_commit();
                    bulk_wait<0>();
                    asm volatile("fence.proxy.async.global;" ::: "memory");
                    if (!redo) asm volatile("red.release.gpu.global.add.u32 [%0], 1;" ::"l"(&g_aocnt) : "memory");
                }
                __syncwarp();
            }
        }
        pdl_launch();
        return;
    }
    uint64_t dq = desc64(((s_q + wg * 4096) >> 4) | (1u << 16)), dq2 = dq + 2;
    uint64_t dkb = desc64((sbase >> 4) | (1u << 16));
    uint64_t dvb = desc64(((sbase + 8192) >> 4) | (((s_ones - sbase - 8192) >> 4) << 16));
    asm volatile("" : "+l"(dkb), "+l"(dvb), "+l"(dq), "+l"(dq2));
    uint32_t Sa[16], Sb[16];
    float O[20];
    uint32_t bad = 0;
    mbar_wait(qbar, 0);
    mbar_wait(s_bar, 0);
    wgmma_fence();
    wgmma_h_ss0_n64(Sa, dq, dkb); wgmma_h_ss_n64(Sa, dq2, dkb + 2, 1);
    wgmma_commit(); wgmma_wait<0>(); fence_regs(Sa);
#pragma unroll 1
    for (int pass = 0; pass < 2; pass++) {
#pragma unroll
        for (int i = 0; i < 20; i++) O[i] = 0.f;
        RowState r0, r1;
        float lo0, lo1;
        { uint32_t a0, a1; local_max(Sa, a0, a1); quad_max(a0, a1, lo0, lo1); row_set(r0, lo0); row_set(r1, lo1); }
#pragma unroll 1
        for (int jj = pass * 16; jj < pass * 16 + 16; jj += ANST) {
#pragma unroll
            for (int u = 0; u < ANST; u++) {
                const int j = jj + u, sn = (u + 1) & (ANST - 1);
                const uint64_t dv = dvb + (uint64_t)(long long)(int)(u * (1024u - (1024u << 16)));
                const uint32_t ok = mbar_try(s_bar + sn * 8, ((j + 1) >> 3) & 1);
                attn_step<PMASK & 0xFFFF>(Sa, Sb, O, r0, r1, dv, dq, dq2, dkb + u * 1024 + 256);
                if (!__all_sync(0xffffffff, ok)) mbar_wait(s_bar + sn * 8, ((j + 1) >> 3) & 1);
                if (j == 15) { mbar_wait(qbar + 8, 0); dq += 1024; dq2 += 1024; }
                wgmma_wait<0>(); fence_regs(Sb); fence_regs(O);
                if (j > 0 && elect_one()) mbar_arrive(s_bar + ANST * 8 + ((u - 1) & (ANST - 1)) * 8);
                attn_step<(PMASK >> 16)>(Sb, Sa, O, r0, r1, dv + 256, dq, dq2, dkb + sn * 1024);
                wgmma_wait<0>(); fence_regs(Sa); fence_regs(O);
            }
        }
        const float i0 = 1.0f / O[16], i1 = 1.0f / O[18];
        {
            float chk = O[16] * 0.f + O[18] * 0.f, x0 = 0.f, x1 = 0.f;
#pragma unroll
            for (int q = 0; q < 4; q++) {
                O[4 * q] *= i0; O[4 * q + 1] *= i0; O[4 * q + 2] *= i1; O[4 * q + 3] *= i1;
                chk = fmaf(O[4 * q], 0.f, chk); chk = fmaf(O[4 * q + 1], 0.f, chk); chk = fmaf(O[4 * q + 2], 0.f, chk); chk = fmaf(O[4 * q + 3], 0.f, chk);
                x0 = fmaxf(x0, fmaxf(fabsf(O[4 * q]), fabsf(O[4 * q + 1]))); x1 = fmaxf(x1, fmaxf(fabsf(O[4 * q + 2]), fabsf(O[4 * q + 3])));
            }
            x0 = fmaxf(x0, __shfl_xor_sync(0xffffffff, x0, 1)); x1 = fmaxf(x1, __shfl_xor_sync(0xffffffff, x1, 1));
            x0 = fmaxf(x0, __shfl_xor_sync(0xffffffff, x0, 2)); x1 = fmaxf(x1, __shfl_xor_sync(0xffffffff, x1, 2));
            const bool m_ok = fminf(lo0, lo1) >= -960.f && fmaxf(r0.mf, r1.mf) <= 2000.f;
            if (!(chk == 0.f) || !(fminf(x0, x1) >= 0.000244140625f) || !m_ok) {
                bad |= 1u << pass;
                asm volatile("st.shared.u32 [%0], 1;" ::"r"(qbar + 16 + pass * 4) : "memory");
            }
        }
        const uint32_t sq = s_q + pass * 16384 + wg * 4096;
        const int row = warp * 16 + (lane & 7) + ((lane >> 3) & 1) * 8;
        named_bar_sync(1 + wg, 128);
#pragma unroll
        for (int j = 0; j < 2; j++) {
            const int ch = j * 2 + (lane >> 4);
            stmatrix_x4(sq + row * 64 + ((ch ^ ((row >> 1) & 3)) << 4), pack_bf16(O[8 * j], O[8 * j + 1]), pack_bf16(O[8 * j + 2], O[8 * j + 3]),
                        pack_bf16(O[8 * j + 4], O[8 * j + 5]), pack_bf16(O[8 * j + 6], O[8 * j + 7]));
        }
        fence_proxy_async();
        if (pass == 0) named_bar_arrive(6 + wg, 160);
        else {
            named_bar_sync(1 + wg, 128);
            if (warp == 0 && elect_one()) { tma_store_2d(&tmO, sq, head_of(1) * 32, qbase + wg * 64); bulk_commit(); }
        }
    }
    if (bar_red_or(bad != 0)) {
        if (warp == 0 && elect_one()) bulk_wait<0>();
        for (int pass = 0; pass < 2; pass++)
            if (bar_red_or((bad >> pass) & 1)) {
                attn_fallback(smem_raw, h, wqkv, ao, head_of(pass), qbase);
                if (pass == 0 && tid == 0) asm volatile("red.release.gpu.global.add.u32 [%0], 1;" ::"l"(&g_aocnt) : "memory");
            }
    }
    if (warp == 0 && elect_one()) bulk_wait_read<0>();
}

typedef CUresult (*PFN_encodeTiled)(CUtensorMap*, CUtensorMapDataType, cuuint32_t, void*, const cuuint64_t*, const cuuint64_t*,
                                    const cuuint32_t*, const cuuint32_t*, CUtensorMapInterleave, CUtensorMapSwizzle,
                                    CUtensorMapL2promotion, CUtensorMapFloatOOBfill);
static PFN_encodeTiled g_encode = nullptr;
static CUtensorMap make_tmap(const void* ptr, uint64_t rows, uint64_t cols, uint32_t box_rows, uint32_t box_cols, CUtensorMapSwizzle swz) {
    CUtensorMap m;
    cuuint64_t dims[2] = {cols, rows};
    cuuint64_t strides[1] = {cols * 2};
    cuuint32_t box[2] = {box_cols, box_rows};
    cuuint32_t es[2] = {1, 1};
    g_encode(&m, CU_TENSOR_MAP_DATA_TYPE_BFLOAT16, 2, (void*)ptr, dims, strides, box, es, CU_TENSOR_MAP_INTERLEAVE_NONE, swz,
             CU_TENSOR_MAP_L2_PROMOTION_L2_256B, CU_TENSOR_MAP_FLOAT_OOB_FILL_NONE);
    return m;
}
template <typename... KArgs, typename... Args>
static void launch(void (*kern)(KArgs...), int grid, int block, int smem, int cluster, bool pdl, Args... args) {
    cudaLaunchConfig_t cfg = {};
    cfg.gridDim = dim3(grid); cfg.blockDim = dim3(block); cfg.dynamicSmemBytes = smem; cfg.stream = cudaStreamPerThread;
    cudaLaunchAttribute at[2]; int n = 0;
    if (cluster > 1) { at[n].id = cudaLaunchAttributeClusterDimension; at[n].val.clusterDim.x = cluster; at[n].val.clusterDim.y = 1; at[n].val.clusterDim.z = 1; n++; }
    if (pdl) { at[n].id = cudaLaunchAttributeProgrammaticStreamSerialization; at[n].val.programmaticStreamSerializationAllowed = 1; n++; }
    cfg.attrs = at; cfg.numAttrs = n;
    cudaLaunchKernelEx(&cfg, kern, args...);
}
template <typename T> static T* sym_ptr(const T& sym) { void* p = nullptr; cudaGetSymbolAddress(&p, sym); return (T*)p; }

extern "C" void kernel_launch(void* const* d_in, const int* in_sizes, int n_in, void* d_out, int out_size) {
    const bf16* x = (const bf16*)d_in[0];
    const bf16* wqkv = (const bf16*)d_in[1];
    const bf16* wo = (const bf16*)d_in[2];
    const bf16* wg = (const bf16*)d_in[4];
    const bf16* wu = (const bf16*)d_in[5];
    const bf16* wd = (const bf16*)d_in[6];
    const bf16* c = (const bf16*)d_in[7];
    const bf16* wmod = (const bf16*)d_in[8];
    if (!g_encode) {
        void* p = nullptr; cudaDriverEntryPointQueryResult q;
        cudaGetDriverEntryPoint("cuTensorMapEncodeTiled", &p, cudaEnableDefault, &q);
        g_encode = (PFN_encodeTiled)p;
        cudaFuncSetAttribute(qkv_kernel, cudaFuncAttributeMaxDynamicSharedMemorySize, QKV_SMEM);
        cudaFuncSetAttribute(tail_kernel, cudaFuncAttributeMaxDynamicSharedMemorySize, TAIL_SMEM);
        cudaFuncSetAttribute(attn_kernel, cudaFuncAttributeMaxDynamicSharedMemorySize, ATTN_SMEM);
    }
    bf16 *h = (bf16*)sym_ptr(g_h), *h2 = (bf16*)sym_ptr(g_h2), *qkv = (bf16*)sym_ptr(g_qkv), *ao = (bf16*)sym_ptr(g_ao), *hh = (bf16*)sym_ptr(g_hh);
    const CUtensorMapSwizzle S128 = CU_TENSOR_MAP_SWIZZLE_128B, S64 = CU_TENSOR_MAP_SWIZZLE_64B;
    CUtensorMap tH = make_tmap(h, S_, D_, 128, 64, S128), tWqkv = make_tmap(wqkv, D_, 3 * D_, 64, 64, S128), tQKVst = make_tmap(qkv, S_, 3 * D_, 64, 64, S128);
    CUtensorMap tQKV = make_tmap(qkv, S_, 3 * D_, 128, 32, S64), tAOst = make_tmap(ao, S_, D_, 64, 32, S64);
    CUtensorMap tAO = make_tmap(ao, S_, D_, 128, 64, S128), tWo = make_tmap(wo, D_, D_, 64, 64, S128), tX = make_tmap(x, S_, D_, 64, 64, S128);
    CUtensorMap tH2 = make_tmap(h2, S_, D_, 128, 64, S128), tWg = make_tmap(wg, D_, F_, 64, 64, S128),
                tWu = make_tmap(wu, D_, F_, 64, 64, S128), tHHst = make_tmap(hh, S_, F_, 64, 64, S128);
    CUtensorMap tHH = make_tmap(hh, S_, F_, 128, 64, S128), tWd = make_tmap(wd, F_, D_, 64, 64, S128), tOut = make_tmap(d_out, S_, D_, 64, 64, S128);

    launch(pre_kernel, 256, 256, 0, 1, false, c, wmod, x, h);
    launch(qkv_kernel, 128, 384, QKV_SMEM, 1, true, tH, tWqkv, tQKVst);
    launch(attn_kernel, 132, 544, ATTN_SMEM, 1, true, tQKV, tAOst, (const bf16*)h, wqkv, ao, c, wmod, wo, wg, wu);
    launch(tail_kernel, 128, 384, TAIL_SMEM, 2, true, tAO, tWo, tX, tH2, tWg, tWu, tHHst, tHH, tWd, tOut, wd, h2);
}
```
